```python
import torch

def _softmax(x, axis=-1):
    return torch.softmax(x, dim=axis)
def _gelu(x):
    return torch.nn.functional.gelu(x, approximate="tanh")
def _silu(x):
    return torch.nn.functional.silu(x)
def _sigmoid(x):
    return torch.sigmoid(x)
def _layernorm(x, axis=-1, eps=1e-5):
    m = x.mean(dim=axis, keepdim=True)
    v = x.var(dim=axis, keepdim=True, unbiased=False)
    return (x - m) / torch.sqrt(v + eps)
def _scatter_add(tgt, idx, src, axis=0):
    return tgt.clone().index_add_(axis, idx, src)
def _segment_sum(src, seg, n):
    out = torch.zeros((n,) + src.shape[1:], dtype=src.dtype)
    return out.index_add_(0, seg, src)
def _pad(x, pw):
    flat = tuple(v for pair in reversed(pw) for v in pair)
    return torch.nn.functional.pad(x, flat)

kernel_name = 'gated_mix__gqa_block_cached__gqa_block_cached__decode'

def setup_inputs():

    _w = (lambda a: (lambda t: t.to(torch.bfloat16) if t.is_floating_point() else t)(torch.as_tensor(a)))
    def _A_setup():
        B, Sq, D = 2, 1, 512
        Hq, Hkv, Sk, Dh = 32, 8, 32768, 128
        assert Hq % Hkv == 0, (Hq, Hkv)
        return {
            "x": _w((lambda *s: torch.randn(*s, dtype=torch.bfloat16) * 0.05)(B, Sq, D)),
            "k_cache": _w((lambda *s: torch.randn(*s, dtype=torch.bfloat16) * 6.4)(B, Hkv, Sk, Dh)),
            "v_cache": _w((lambda *s: torch.randn(*s, dtype=torch.bfloat16) * 0.05)(B, Hkv, Sk, Dh)),
            "wq": _w((lambda *s: torch.randn(*s, dtype=torch.bfloat16) * 6.4)(D, Hq * Dh) * (D ** -0.5)),
            "wo": _w((lambda *s: torch.randn(*s, dtype=torch.bfloat16) * 0.05)(Hq * Dh, D) * ((Hq * Dh) ** -0.5)),
        }
    _A_in = _A_setup()

    def _B_setup():
        B, Sq, D = 2, 1, 512
        Hq, Hkv, Sk, Dh = 32, 8, 32768, 128
        assert Hq % Hkv == 0, (Hq, Hkv)
        return {
            "x": _w((lambda *s: torch.randn(*s, dtype=torch.bfloat16) * 0.05)(B, Sq, D)),
            "k_cache": _w((lambda *s: torch.randn(*s, dtype=torch.bfloat16) * 6.4)(B, Hkv, Sk, Dh)),
            "v_cache": _w((lambda *s: torch.randn(*s, dtype=torch.bfloat16) * 0.05)(B, Hkv, Sk, Dh)),
            "wq": _w((lambda *s: torch.randn(*s, dtype=torch.bfloat16) * 6.4)(D, Hq * Dh) * (D ** -0.5)),
            "wo": _w((lambda *s: torch.randn(*s, dtype=torch.bfloat16) * 0.05)(Hq * Dh, D) * ((Hq * Dh) ** -0.5)),
        }
    _B_in = _B_setup()

    return {
        "A_x": _A_in["x"],
        "A_k_cache": _A_in["k_cache"],
        "A_v_cache": _A_in["v_cache"],
        "A_wq": _A_in["wq"],
        "A_wo": _A_in["wo"],
        "B_x": _B_in["x"],
        "B_k_cache": _B_in["k_cache"],
        "B_v_cache": _B_in["v_cache"],
        "B_wq": _B_in["wq"],
        "B_wo": _B_in["wo"],
        "gate_w": _w((lambda *s: torch.randn(*s, dtype=torch.bfloat16) * 0.1)(512) * 16.0),
    }

def reference(A_x, A_k_cache, A_v_cache, A_wq, A_wo, B_x, B_k_cache, B_v_cache, B_wq, B_wo, gate_w):
    def _A_ref(x, k_cache, v_cache, wq, wo):
        B, Sq, D = x.shape
        Hq, Dh = 32, 128
        Hkv = k_cache.shape[1]
        rep = Hq // Hkv
        q = (lambda x, *d: x.permute(*d))((x @ wq).reshape(B, Sq, Hq, Dh), 0, 2, 1, 3)
        k = (lambda x, n, axis: torch.repeat_interleave(x, n, dim=axis))(k_cache, rep, axis=1)
        v = (lambda x, n, axis: torch.repeat_interleave(x, n, dim=axis))(v_cache, rep, axis=1)
        scores = torch.einsum("bhqd,bhkd->bhqk", q, k) * (Dh ** -0.5)
        p = _softmax(scores, axis=-1)
        o = torch.einsum("bhqk,bhkd->bhqd", p, v)
        return (lambda x, *d: x.permute(*d))(o, 0, 2, 1, 3).reshape(B, Sq, Hq * Dh) @ wo

    def _B_ref(x, k_cache, v_cache, wq, wo):
        B, Sq, D = x.shape
        Hq, Dh = 32, 128
        Hkv = k_cache.shape[1]
        rep = Hq // Hkv
        q = (lambda x, *d: x.permute(*d))((x @ wq).reshape(B, Sq, Hq, Dh), 0, 2, 1, 3)
        k = (lambda x, n, axis: torch.repeat_interleave(x, n, dim=axis))(k_cache, rep, axis=1)
        v = (lambda x, n, axis: torch.repeat_interleave(x, n, dim=axis))(v_cache, rep, axis=1)
        scores = torch.einsum("bhqd,bhkd->bhqk", q, k) * (Dh ** -0.5)
        p = _softmax(scores, axis=-1)
        o = torch.einsum("bhqk,bhkd->bhqd", p, v)
        return (lambda x, *d: x.permute(*d))(o, 0, 2, 1, 3).reshape(B, Sq, Hq * Dh) @ wo

    x = A_x
    g = _sigmoid((x * gate_w).sum(-1, keepdims=True))
    a = _A_ref(x, A_k_cache, A_v_cache, A_wq, A_wo)
    b = _B_ref(x, B_k_cache, B_v_cache, B_wq, B_wo)
    return g * a + (1 - g) * b
```

```cpp
#include <cuda_runtime.h>
#include <cuda_bf16.h>
#include <cuda.h>
#include <stdint.h>

namespace {

constexpr int kD      = 512;
constexpr int kHq     = 32;
constexpr int kHkv    = 8;
constexpr int kSk     = 32768;
constexpr int kDh     = 128;
constexpr int kSplits = 4;
constexpr int kKeysPerCta = kSk / kSplits;
constexpr int kTileKeys   = 128;
constexpr int kTiles      = kKeysPerCta / kTileKeys;
constexpr int kSlotBytes  = kTileKeys * kDh * 2;
#define NSLOT 6
constexpr int kNSlot   = NSLOT;
constexpr int kNCta    = 128;
constexpr int kCWarps  = 8;
constexpr int kThreads = (kCWarps + 1) * 32;
constexpr int kNLoads  = 2 * kTiles + 2;

constexpr int kOffRing = 0;
constexpr int kOffO    = kNSlot * kSlotBytes;
constexpr int kOffML   = kOffO + kCWarps * 4 * 128 * 4;
constexpr int kOffSo   = kOffML + 256;
constexpr int kOffRed  = kOffSo + 512;
constexpr int kOffGate = kOffRed + 256;
constexpr int kOffBar  = kOffGate + 16;
constexpr int kSmemBytes = kOffBar + 2 * kNSlot * 8 + 1024;

constexpr float kScaleLog2 = 0.08838834764831845f * 1.4426950408889634f;

__device__ unsigned int g_epoch;
__device__ __align__(16) unsigned long long g_qx[16][2][256];
__device__ __align__(16) unsigned long long g_px[kNCta][4][132];
__device__ __align__(16) unsigned long long g_fo[kNCta][kNCta][8];

__device__ __forceinline__ uint32_t smem_u32(const void* p) { return (uint32_t)__cvta_generic_to_shared(p); }

__device__ __forceinline__ void mbar_init(uint32_t bar, uint32_t cnt) {
    asm volatile("mbarrier.init.shared::cta.b64 [%0], %1;" :: "r"(bar), "r"(cnt) : "memory");
}
__device__ __forceinline__ void mbar_expect_tx(uint32_t bar, uint32_t bytes) {
    asm volatile("mbarrier.arrive.expect_tx.shared::cta.b64 _, [%0], %1;" :: "r"(bar), "r"(bytes) : "memory");
}
__device__ __forceinline__ void mbar_arrive(uint32_t bar) {
    asm volatile("mbarrier.arrive.shared::cta.b64 _, [%0];" :: "r"(bar) : "memory");
}
__device__ __forceinline__ void mbar_wait(uint32_t bar, uint32_t parity) {
    uint32_t done;
    uint32_t iters = 0;
    while (true) {
        asm volatile("{\n.reg .pred p;\n"
                     "mbarrier.try_wait.parity.shared::cta.b64 p, [%1], %2;\n"
                     "selp.u32 %0, 1, 0, p;\n}"
                     : "=r"(done) : "r"(bar), "r"(parity) : "memory");
        if (done) break;
        if (++iters > (1u << 24)) __trap();
    }
}
__device__ __forceinline__ void tma_load_3d(uint32_t dst, const CUtensorMap* map, uint32_t bar, int c0, int c1, int c2) {
    asm volatile("cp.async.bulk.tensor.3d.shared::cluster.global.mbarrier::complete_tx::bytes "
                 "[%0], [%1, {%3, %4, %5}], [%2];"
                 :: "r"(dst), "l"(map), "r"(bar), "r"(c0), "r"(c1), "r"(c2) : "memory");
}
__device__ __forceinline__ void ldsm_x4(uint32_t& r0, uint32_t& r1, uint32_t& r2, uint32_t& r3, uint32_t addr) {
    asm volatile("ldmatrix.sync.aligned.m8n8.x4.shared.b16 {%0,%1,%2,%3}, [%4];"
                 : "=r"(r0), "=r"(r1), "=r"(r2), "=r"(r3) : "r"(addr) : "memory");
}
__device__ __forceinline__ void ldsm_x4_t(uint32_t& r0, uint32_t& r1, uint32_t& r2, uint32_t& r3, uint32_t addr) {
    asm volatile("ldmatrix.sync.aligned.m8n8.x4.trans.shared.b16 {%0,%1,%2,%3}, [%4];"
                 : "=r"(r0), "=r"(r1), "=r"(r2), "=r"(r3) : "r"(addr) : "memory");
}
__device__ __forceinline__ void mma_bf16(float (&c)[4], uint32_t a0, uint32_t a1, uint32_t a2, uint32_t a3,
                                         uint32_t b0, uint32_t b1) {
    asm volatile("mma.sync.aligned.m16n8k16.row.col.f32.bf16.bf16.f32 "
                 "{%0,%1,%2,%3}, {%4,%5,%6,%7}, {%8,%9}, {%0,%1,%2,%3};"
                 : "+f"(c[0]), "+f"(c[1]), "+f"(c[2]), "+f"(c[3])
                 : "r"(a0), "r"(a1), "r"(a2), "r"(a3), "r"(b0), "r"(b1));
}
__device__ __forceinline__ uint32_t movmatrix_t(uint32_t a) {
    uint32_t d;
    asm volatile("movmatrix.sync.aligned.m8n8.trans.b16 %0, %1;" : "=r"(d) : "r"(a));
    return d;
}
__device__ __forceinline__ uint32_t pack_bf16(float lo, float hi) {
    uint32_t r;
    asm("cvt.rn.bf16x2.f32 %0, %1, %2;" : "=r"(r) : "f"(hi), "f"(lo));
    return r;
}
__device__ __forceinline__ float bf16lo(uint32_t v) { return __uint_as_float(v << 16); }
__device__ __forceinline__ float bf16hi(uint32_t v) { return __uint_as_float(v & 0xffff0000u); }
__device__ __forceinline__ float ex2(float x) {
    float y;
    asm("ex2.approx.ftz.f32 %0, %1;" : "=f"(y) : "f"(x));
    return y;
}
__device__ __forceinline__ unsigned long long ll_word(uint32_t payload, uint32_t tag) {
    return ((unsigned long long)tag << 32) | payload;
}
__device__ __forceinline__ void ll_st1(unsigned long long* p, unsigned long long a) {
    asm volatile("st.relaxed.gpu.global.b64 [%0], %1;" :: "l"(p), "l"(a) : "memory");
}
__device__ __forceinline__ void ll_st2(unsigned long long* p, unsigned long long a, unsigned long long b) {
    asm volatile("st.relaxed.gpu.global.v2.b64 [%0], {%1, %2};" :: "l"(p), "l"(a), "l"(b) : "memory");
}
__device__ __forceinline__ void ll_ld2(const unsigned long long* p, unsigned long long& a, unsigned long long& b) {
    asm volatile("ld.relaxed.gpu.global.v2.b64 {%0, %1}, [%2];" : "=l"(a), "=l"(b) : "l"(p) : "memory");
}
__device__ __forceinline__ uint4 ldg_nc_v4(const void* p) {
    uint4 v;
    asm volatile("ld.global.nc.L1::no_allocate.v4.u32 {%0,%1,%2,%3}, [%4];"
                 : "=r"(v.x), "=r"(v.y), "=r"(v.z), "=r"(v.w) : "l"(p) : "memory");
    return v;
}
__device__ __forceinline__ void consumer_bar() {
    asm volatile("bar.sync 1, 256;" ::: "memory");
}

struct Params {
    const __nv_bfloat16* x;
    const __nv_bfloat16* wq[2];
    const __nv_bfloat16* gate_w;
    __nv_bfloat16* out;
};

__global__ void __launch_bounds__(kThreads, 1)
fused_decode_kernel(const __grid_constant__ CUtensorMap mapKA, const __grid_constant__ CUtensorMap mapVA,
                    const __grid_constant__ CUtensorMap mapKB, const __grid_constant__ CUtensorMap mapVB,
                    const __grid_constant__ CUtensorMap mapWoA, const __grid_constant__ CUtensorMap mapWoB,
                    const Params prm) {
    extern __shared__ __align__(16) unsigned char smem_raw[];
    const uint32_t sbase = (smem_u32(smem_raw) + 1023u) & ~1023u;
    unsigned char* sptr = smem_raw + (sbase - smem_u32(smem_raw));

    const int tid  = threadIdx.x;
    const int warp = tid >> 5;
    const int lane = tid & 31;
    const int cta  = blockIdx.x;
    const int mod  = cta >> 6;
    const int kvh  = (cta >> 3) & 7;
    const int r    = cta & 7;
    const int bat  = r >> 2;
    const int spl  = r & 3;
    const int grp  = cta >> 3;

    const uint32_t bar_full  = sbase + kOffBar;
    const uint32_t bar_empty = bar_full + kNSlot * 8;

    if (warp == kCWarps) {
        if (lane == 0) {
            for (int s = 0; s < kNSlot; s++) {
                mbar_init(bar_full + s * 8, 1);
                mbar_init(bar_empty + s * 8, kCWarps);
            }
            asm volatile("fence.mbarrier_init.release.cluster;" ::: "memory");
        }
        __syncthreads();
        if (lane == 0) {
            const CUtensorMap* mk = mod ? &mapKB : &mapKA;
            const CUtensorMap* mv = mod ? &mapVB : &mapVA;
            const CUtensorMap* mw = mod ? &mapWoB : &mapWoA;
            const int row0 = (bat * kHkv + kvh) * kSk + spl * kKeysPerCta;
            int slot = 0;
            uint32_t ph = 1;
            for (int t = 0; t < kNLoads; t++) {
                mbar_wait(bar_empty + slot * 8, ph);
                const uint32_t fb = bar_full + slot * 8;
                mbar_expect_tx(fb, kSlotBytes);
                const uint32_t dst = sbase + kOffRing + slot * kSlotBytes;
                if (t < 2 * kTiles) {
                    tma_load_3d(dst, (t & 1) ? mv : mk, fb, 0, row0 + (t >> 1) * kTileKeys, 0);
                } else {
                    tma_load_3d(dst, mw, fb, 0, kvh * 512 + r * 64 + (t - 2 * kTiles) * 32, 0);
                }
                if (++slot == kNSlot) { slot = 0; ph ^= 1; }
            }
        }
        return;
    }

    const int g = lane >> 2;
    const int tq = lane & 3;

    const uint32_t tag = *(volatile unsigned int*)&g_epoch + 1u;
    {
        const int c8 = tid & 7;
        const int rg = tid >> 3;
        const __nv_bfloat16* wp = prm.wq[mod] + (size_t)(rg * 16) * (kHq * kDh) + kvh * 512 + r * 64 + c8 * 8;
        uint4 w[16];
#pragma unroll
        for (int k = 0; k < 16; k++) w[k] = ldg_nc_v4(wp + (size_t)k * (kHq * kDh));
        uint4 xv[2][2];
#pragma unroll
        for (int b = 0; b < 2; b++) {
            xv[b][0] = *reinterpret_cast<const uint4*>(prm.x + b * kD + rg * 16);
            xv[b][1] = *reinterpret_cast<const uint4*>(prm.x + b * kD + rg * 16 + 8);
        }
        __syncthreads();

        float acc[2][8];
#pragma unroll
        for (int b = 0; b < 2; b++)
#pragma unroll
            for (int j = 0; j < 8; j++) acc[b][j] = 0.f;
#pragma unroll
        for (int k = 0; k < 16; k++) {
            const uint32_t wv[4] = {w[k].x, w[k].y, w[k].z, w[k].w};
#pragma unroll
            for (int b = 0; b < 2; b++) {
                const uint4 xx = xv[b][k >> 3];
                const uint32_t xw = ((k >> 1) & 3) == 0 ? xx.x : ((k >> 1) & 3) == 1 ? xx.y : ((k >> 1) & 3) == 2 ? xx.z : xx.w;
                const float xf = (k & 1) ? bf16hi(xw) : bf16lo(xw);
#pragma unroll
                for (int j = 0; j < 4; j++) {
                    acc[b][2 * j]     = fmaf(xf, bf16lo(wv[j]), acc[b][2 * j]);
                    acc[b][2 * j + 1] = fmaf(xf, bf16hi(wv[j]), acc[b][2 * j + 1]);
                }
            }
        }
#pragma unroll
        for (int b = 0; b < 2; b++)
#pragma unroll
            for (int j = 0; j < 8; j++) {
                acc[b][j] += __shfl_xor_sync(0xffffffffu, acc[b][j], 8);
                acc[b][j] += __shfl_xor_sync(0xffffffffu, acc[b][j], 16);
            }
        float* red = reinterpret_cast<float*>(sptr + kOffO);
        if (lane < 8) {
#pragma unroll
            for (int b = 0; b < 2; b++) {
                float4* d4 = reinterpret_cast<float4*>(red + (warp * 2 + b) * 64 + lane * 8);
                d4[0] = make_float4(acc[b][0], acc[b][1], acc[b][2], acc[b][3]);
                d4[1] = make_float4(acc[b][4], acc[b][5], acc[b][6], acc[b][7]);
            }
        }
        consumer_bar();
        if (tid < 64) {
            const int b = tid >> 5, i = tid & 31;
            float s0 = 0.f, s1 = 0.f;
#pragma unroll
            for (int w8 = 0; w8 < kCWarps; w8++) {
                const float2 v = *reinterpret_cast<const float2*>(red + (w8 * 2 + b) * 64 + 2 * i);
                s0 += v.x; s1 += v.y;
            }
            const int col = r * 64 + 2 * i;
            const int head = col >> 7, p = (col & 127) >> 1;
            const int pos = head * 64 + (p >> 3) * 8 + (p & 3) * 2 + ((p >> 2) & 1);
            ll_st1(&g_qx[grp][b][pos], ll_word(pack_bf16(s0, s1), tag));
        } else if (warp == 2) {
            float s[2] = {0.f, 0.f};
#pragma unroll
            for (int h = 0; h < 2; h++) {
                const uint4 gw = *reinterpret_cast<const uint4*>(prm.gate_w + (h * 32 + lane) * 8);
                const uint32_t gv[4] = {gw.x, gw.y, gw.z, gw.w};
#pragma unroll
                for (int b = 0; b < 2; b++) {
                    const uint4 xx = *reinterpret_cast<const uint4*>(prm.x + b * kD + (h * 32 + lane) * 8);
                    const uint32_t xw[4] = {xx.x, xx.y, xx.z, xx.w};
#pragma unroll
                    for (int j = 0; j < 4; j++) {
                        s[b] = fmaf(bf16lo(gv[j]), bf16lo(xw[j]), s[b]);
                        s[b] = fmaf(bf16hi(gv[j]), bf16hi(xw[j]), s[b]);
                    }
                }
            }
#pragma unroll
            for (int o = 16; o > 0; o >>= 1) {
                s[0] += __shfl_xor_sync(0xffffffffu, s[0], o);
                s[1] += __shfl_xor_sync(0xffffffffu, s[1], o);
            }
            if (lane < 2) {
                const float z = lane ? s[1] : s[0];
                const float gt = 1.f / (1.f + __expf(-z));
                reinterpret_cast<float*>(sptr + kOffGate)[lane] = mod ? (1.f - gt) : gt;
            }
        }
    }

    uint32_t bq[8][2];
    {
        const unsigned long long* qp = &g_qx[grp][bat][(g & 3) * 64 + tq * 2];
        uint32_t iters = 0;
        while (true) {
            bool ok = true;
#pragma unroll
            for (int ks = 0; ks < 8; ks++) {
                unsigned long long a, b;
                ll_ld2(qp + ks * 8, a, b);
                bq[ks][0] = (uint32_t)a; bq[ks][1] = (uint32_t)b;
                ok = ok && (uint32_t)(a >> 32) == tag && (uint32_t)(b >> 32) == tag;
            }
            if (__all_sync(0xffffffffu, ok)) break;
            if (++iters > (1u << 22)) __trap();
        }
        if (g >= 4) {
#pragma unroll
            for (int ks = 0; ks < 8; ks++) { bq[ks][0] = 0u; bq[ks][1] = 0u; }
        }
    }

    float o[8][4];
#pragma unroll
    for (int i = 0; i < 8; i++) { o[i][0] = 0.f; o[i][1] = 0.f; o[i][2] = 0.f; o[i][3] = 0.f; }
    float m0 = -INFINITY, m1 = -INFINITY, l0 = 0.f, l1 = 0.f;

    const int mi = lane >> 3, rr = lane & 7;
    const uint32_t kRowOff = (uint32_t)(warp * 16 + rr + (mi & 1) * 8) * 128u;
    const uint32_t kChunk  = (uint32_t)(mi >> 1);
    const uint32_t vRowOff = (uint32_t)(warp * 16 + rr + (mi >> 1) * 8) * 128u;
    const uint32_t vChunk  = (uint32_t)(mi & 1);
    const uint32_t sw = (uint32_t)rr;

    int slot = 0;
    uint32_t ph = 0;
#pragma unroll 1
    for (int tile = 0; tile < kTiles; tile++) {
        mbar_wait(bar_full + slot * 8, ph);
        float s[4] = {0.f, 0.f, 0.f, 0.f};
        float s2[4] = {0.f, 0.f, 0.f, 0.f};
        {
            const uint32_t kb = sbase + kOffRing + slot * kSlotBytes + kRowOff;
#pragma unroll
            for (int ks = 0; ks < 8; ks++) {
                uint32_t a0, a1, a2, a3;
                const uint32_t ch = ((uint32_t)((2 * ks) & 7) + kChunk) ^ sw;
                ldsm_x4(a0, a1, a2, a3, kb + (ks >> 2) * 16384 + ch * 16);
                if (ks & 1) mma_bf16(s2, a0, a1, a2, a3, bq[ks][0], bq[ks][1]);
                else        mma_bf16(s,  a0, a1, a2, a3, bq[ks][0], bq[ks][1]);
            }
        }
        __syncwarp();
        if (lane == 0) mbar_arrive(bar_empty + slot * 8);
        if (++slot == kNSlot) { slot = 0; ph ^= 1; }
#pragma unroll
        for (int i = 0; i < 4; i++) s[i] += s2[i];

        float x0 = fmaxf(s[0], s[2]), x1 = fmaxf(s[1], s[3]);
#pragma unroll
        for (int off = 4; off <= 16; off <<= 1) {
            x0 = fmaxf(x0, __shfl_xor_sync(0xffffffffu, x0, off));
            x1 = fmaxf(x1, __shfl_xor_sync(0xffffffffu, x1, off));
        }
        if (__any_sync(0xffffffffu, (x0 > m0) || (x1 > m1))) {
            const float n0 = fmaxf(m0, x0), n1 = fmaxf(m1, x1);
            const float a0 = ex2((m0 - n0) * kScaleLog2), a1 = ex2((m1 - n1) * kScaleLog2);
            m0 = n0; m1 = n1;
            l0 *= a0; l1 *= a1;
#pragma unroll
            for (int i = 0; i < 8; i++) { o[i][0] *= a0; o[i][1] *= a1; o[i][2] *= a0; o[i][3] *= a1; }
        }
        const float mc0 = m0 * kScaleLog2, mc1 = m1 * kScaleLog2;
        const float p0 = ex2(fmaf(s[0], kScaleLog2, -mc0));
        const float p1 = ex2(fmaf(s[1], kScaleLog2, -mc1));
        const float p2 = ex2(fmaf(s[2], kScaleLog2, -mc0));
        const float p3 = ex2(fmaf(s[3], kScaleLog2, -mc1));
        l0 += p0 + p2;
        l1 += p1 + p3;
        const uint32_t pb0 = movmatrix_t(pack_bf16(p0, p1));
        const uint32_t pb1 = movmatrix_t(pack_bf16(p2, p3));

        mbar_wait(bar_full + slot * 8, ph);
        {
            const uint32_t vb = sbase + kOffRing + slot * kSlotBytes + vRowOff;
#pragma unroll
            for (int mt = 0; mt < 8; mt++) {
                uint32_t a0, a1, a2, a3;
                const uint32_t ch = ((uint32_t)((2 * mt) & 7) + vChunk) ^ sw;
                ldsm_x4_t(a0, a1, a2, a3, vb + (mt >> 2) * 16384 + ch * 16);
                mma_bf16(o[mt], a0, a1, a2, a3, pb0, pb1);
            }
        }
        __syncwarp();
        if (lane == 0) mbar_arrive(bar_empty + slot * 8);
        if (++slot == kNSlot) { slot = 0; ph ^= 1; }
    }

    {
        float* so  = reinterpret_cast<float*>(sptr + kOffO);
        float* sml = reinterpret_cast<float*>(sptr + kOffML);
#pragma unroll
        for (int off = 4; off <= 16; off <<= 1) {
            l0 += __shfl_xor_sync(0xffffffffu, l0, off);
            l1 += __shfl_xor_sync(0xffffffffu, l1, off);
        }
        if (tq < 2) {
            float* d0 = so + (warp * 4 + 2 * tq) * 128 + g;
#pragma unroll
            for (int mt = 0; mt < 8; mt++) {
                d0[mt * 16]           = o[mt][0];
                d0[128 + mt * 16]     = o[mt][1];
                d0[mt * 16 + 8]       = o[mt][2];
                d0[128 + mt * 16 + 8] = o[mt][3];
            }
            if (g == 0) {
                sml[warp * 4 + 2 * tq] = m0;      sml[warp * 4 + 2 * tq + 1] = m1;
                sml[32 + warp * 4 + 2 * tq] = l0; sml[32 + warp * 4 + 2 * tq + 1] = l1;
            }
        }
        consumer_bar();
        const int h = tid >> 6, dp = tid & 63;
        float M = -INFINITY;
#pragma unroll
        for (int w8 = 0; w8 < kCWarps; w8++) M = fmaxf(M, sml[w8 * 4 + h]);
        float L = 0.f, a0 = 0.f, a1 = 0.f;
#pragma unroll
        for (int w8 = 0; w8 < kCWarps; w8++) {
            const float wgt = ex2((sml[w8 * 4 + h] - M) * kScaleLog2);
            L = fmaf(wgt, sml[32 + w8 * 4 + h], L);
            const float2 v = *reinterpret_cast<const float2*>(so + (w8 * 4 + h) * 128 + 2 * dp);
            a0 = fmaf(wgt, v.x, a0); a1 = fmaf(wgt, v.y, a1);
        }
        ll_st2(&g_px[cta][h][2 * dp], ll_word(__float_as_uint(a0), tag), ll_word(__float_as_uint(a1), tag));
        if (dp == 0) ll_st2(&g_px[cta][h][128], ll_word(__float_as_uint(M), tag), ll_word(__float_as_uint(L), tag));
    }

    if (tid < 64) {
        const int b = tid >> 5, dp = tid & 31;
        const int h = r >> 1, hf = r & 1;
        float ov[4][2], mv[4], lv[4];
        uint32_t iters = 0;
        while (true) {
            bool ok = true;
#pragma unroll
            for (int s = 0; s < 4; s++) {
                const unsigned long long* src = &g_px[grp * 8 + b * 4 + s][h][0];
                unsigned long long a, c, m, l;
                ll_ld2(src + hf * 64 + dp * 2, a, c);
                ll_ld2(src + 128, m, l);
                ov[s][0] = __uint_as_float((uint32_t)a); ov[s][1] = __uint_as_float((uint32_t)c);
                mv[s] = __uint_as_float((uint32_t)m);    lv[s] = __uint_as_float((uint32_t)l);
                ok = ok && (uint32_t)(a >> 32) == tag && (uint32_t)(c >> 32) == tag &&
                     (uint32_t)(m >> 32) == tag && (uint32_t)(l >> 32) == tag;
            }
            if (__all_sync(0xffffffffu, ok)) break;
            if (++iters > (1u << 22)) __trap();
        }
        const float M = fmaxf(fmaxf(mv[0], mv[1]), fmaxf(mv[2], mv[3]));
        float L = 0.f, a0 = 0.f, a1 = 0.f;
#pragma unroll
        for (int s = 0; s < 4; s++) {
            const float wgt = ex2((mv[s] - M) * kScaleLog2);
            L = fmaf(wgt, lv[s], L);
            a0 = fmaf(wgt, ov[s][0], a0); a1 = fmaf(wgt, ov[s][1], a1);
        }
        const float sc = reinterpret_cast<const float*>(sptr + kOffGate)[b] / L;
        a0 *= sc; a1 *= sc;
        const uint32_t hi = pack_bf16(a0, a1);
        const uint32_t lo = pack_bf16(a0 - bf16lo(hi), a1 - bf16hi(hi));
        uint32_t* sob = reinterpret_cast<uint32_t*>(sptr + kOffSo);
        sob[(2 * b) * 32 + dp] = hi;
        sob[(2 * b + 1) * 32 + dp] = lo;
    }
    consumer_bar();

    {
        float c[4][4];
#pragma unroll
        for (int i = 0; i < 4; i++) { c[i][0] = 0.f; c[i][1] = 0.f; c[i][2] = 0.f; c[i][3] = 0.f; }
        const uint32_t* sob = reinterpret_cast<const uint32_t*>(sptr + kOffSo);
#pragma unroll
        for (int hfj = 0; hfj < 2; hfj++) {
            mbar_wait(bar_full + slot * 8, ph);
            const uint32_t wb = sbase + kOffRing + slot * kSlotBytes + warp * 4096;
#pragma unroll
            for (int k2 = 0; k2 < 2; k2++) {
                const int ks = hfj * 2 + k2;
                uint32_t b0 = 0u, b1 = 0u;
                if (g < 4) { b0 = sob[g * 32 + ks * 8 + tq]; b1 = sob[g * 32 + ks * 8 + 4 + tq]; }
                const uint32_t rowoff = (uint32_t)(k2 * 16 + rr + (mi >> 1) * 8) * 128u;
#pragma unroll
                for (int mt = 0; mt < 4; mt++) {
                    uint32_t a0, a1, a2, a3;
                    const uint32_t ch = ((uint32_t)(2 * mt) + vChunk) ^ sw;
                    ldsm_x4_t(a0, a1, a2, a3, wb + rowoff + ch * 16);
                    mma_bf16(c[mt], a0, a1, a2, a3, b0, b1);
                }
            }
            if (++slot == kNSlot) { slot = 0; ph ^= 1; }
        }
        if (tq < 2) {
#pragma unroll
            for (int mt = 0; mt < 4; mt++) {
                const int dest = ((tq * 32 + warp * 4 + mt) << 1) + (g >> 2);
                ll_st2(&g_fo[dest][cta][(g & 3) * 2],
                       ll_word(__float_as_uint(c[mt][0] + c[mt][1]), tag),
                       ll_word(__float_as_uint(c[mt][2] + c[mt][3]), tag));
            }
        }
    }

    {
        const int w4 = tid & 3, src = tid >> 2;
        float v0, v1;
        uint32_t iters = 0;
        while (true) {
            unsigned long long a, b, c, d;
            ll_ld2(&g_fo[cta][src][w4 * 2], a, b);
            ll_ld2(&g_fo[cta][src + 64][w4 * 2], c, d);
            v0 = __uint_as_float((uint32_t)a) + __uint_as_float((uint32_t)c);
            v1 = __uint_as_float((uint32_t)b) + __uint_as_float((uint32_t)d);
            const bool ok = (uint32_t)(a >> 32) == tag && (uint32_t)(b >> 32) == tag &&
                            (uint32_t)(c >> 32) == tag && (uint32_t)(d >> 32) == tag;
            if (__all_sync(0xffffffffu, ok)) break;
            if (++iters > (1u << 22)) __trap();
        }
#pragma unroll
        for (int off = 4; off <= 16; off <<= 1) {
            v0 += __shfl_xor_sync(0xffffffffu, v0, off);
            v1 += __shfl_xor_sync(0xffffffffu, v1, off);
        }
        float* red = reinterpret_cast<float*>(sptr + kOffRed);
        if (lane < 4) { red[warp * 8 + lane * 2] = v0; red[warp * 8 + lane * 2 + 1] = v1; }
        consumer_bar();
        if (tid < 8) {
            float sum = 0.f;
#pragma unroll
            for (int w8 = 0; w8 < kCWarps; w8++) sum += red[w8 * 8 + tid];
            const int b = cta >> 6, mtile = (cta >> 1) & 31, gh = cta & 1;
            const int n = mtile * 16 + gh * 4 + (tid >> 1) + (tid & 1) * 8;
            prm.out[b * kD + n] = __float2bfloat16(sum);
        }
        if (cta == 0 && tid == 0) *(volatile unsigned int*)&g_epoch = tag;
    }
}

typedef CUresult (*EncodeTiledFn)(CUtensorMap*, CUtensorMapDataType, cuuint32_t, void*, const cuuint64_t*,
                                  const cuuint64_t*, const cuuint32_t*, const cuuint32_t*, CUtensorMapInterleave,
                                  CUtensorMapSwizzle, CUtensorMapL2promotion, CUtensorMapFloatOOBfill);

void make_kv_map(EncodeTiledFn enc, CUtensorMap* m, const void* base) {
    cuuint64_t gd[3] = {64, (cuuint64_t)2 * kHkv * kSk, 2};
    cuuint64_t gs[2] = {256, 128};
    cuuint32_t box[3] = {64, (cuuint32_t)kTileKeys, 2};
    cuuint32_t es[3] = {1, 1, 1};
    enc(m, CU_TENSOR_MAP_DATA_TYPE_BFLOAT16, 3, const_cast<void*>(base), gd, gs, box, es,
        CU_TENSOR_MAP_INTERLEAVE_NONE, CU_TENSOR_MAP_SWIZZLE_128B, CU_TENSOR_MAP_L2_PROMOTION_L2_256B,
        CU_TENSOR_MAP_FLOAT_OOB_FILL_NONE);
}
void make_wo_map(EncodeTiledFn enc, CUtensorMap* m, const void* base) {
    cuuint64_t gd[3] = {64, (cuuint64_t)kHq * kDh, 8};
    cuuint64_t gs[2] = {1024, 128};
    cuuint32_t box[3] = {64, 32, 8};
    cuuint32_t es[3] = {1, 1, 1};
    enc(m, CU_TENSOR_MAP_DATA_TYPE_BFLOAT16, 3, const_cast<void*>(base), gd, gs, box, es,
        CU_TENSOR_MAP_INTERLEAVE_NONE, CU_TENSOR_MAP_SWIZZLE_128B, CU_TENSOR_MAP_L2_PROMOTION_L2_256B,
        CU_TENSOR_MAP_FLOAT_OOB_FILL_NONE);
}

}

extern "C" void kernel_launch(void* const* d_in, const int* in_sizes, int n_in, void* d_out, int out_size) {
    (void)in_sizes; (void)n_in; (void)out_size;
    static EncodeTiledFn enc = nullptr;
    if (!enc) {
        void* fn = nullptr;
        cudaDriverEntryPointQueryResult qr;
        cudaGetDriverEntryPoint("cuTensorMapEncodeTiled", &fn, cudaEnableDefault, &qr);
        enc = (EncodeTiledFn)fn;
        cudaFuncSetAttribute(fused_decode_kernel, cudaFuncAttributeMaxDynamicSharedMemorySize, kSmemBytes);
    }
    CUtensorMap mKA, mVA, mKB, mVB, mWA, mWB;
    make_kv_map(enc, &mKA, d_in[1]);
    make_kv_map(enc, &mVA, d_in[2]);
    make_kv_map(enc, &mKB, d_in[6]);
    make_kv_map(enc, &mVB, d_in[7]);
    make_wo_map(enc, &mWA, d_in[4]);
    make_wo_map(enc, &mWB, d_in[9]);
    Params p;
    p.x = (const __nv_bfloat16*)d_in[0];
    p.wq[0] = (const __nv_bfloat16*)d_in[3];
    p.wq[1] = (const __nv_bfloat16*)d_in[8];
    p.gate_w = (const __nv_bfloat16*)d_in[10];
    p.out = (__nv_bfloat16*)d_out;
    fused_decode_kernel<<<kNCta, kThreads, kSmemBytes>>>(mKA, mVA, mKB, mVB, mWA, mWB, p);
}
```

```cpp
#include <cuda_runtime.h>
#include <cuda_bf16.h>
#include <cuda.h>
#include <stdint.h>

namespace {

constexpr int kD      = 512;
constexpr int kHq     = 32;
constexpr int kHkv    = 8;
constexpr int kSk     = 32768;
constexpr int kDh     = 128;
constexpr int kBlkKeys    = 64;
constexpr int kBlkPerUnit = kSk / kBlkKeys;
constexpr int kNUnits     = 32;
constexpr int kTotalBlk   = kNUnits * kBlkPerUnit;
constexpr int kTileBytes  = kBlkKeys * kDh * 2;
constexpr int kSlotBytes  = 2 * kTileBytes;
constexpr int kNSlot   = 5;
constexpr int kFlight  = 3;
constexpr int kNCta    = 128;
constexpr int kThreads = 9 * 32;

constexpr int kStgBytes = 4 * 4 * 128 * 4 + 4 * 8 * 4;
constexpr int kOffRing = 0;
constexpr int kOffQ    = kNSlot * kSlotBytes;
constexpr int kOffStg  = kOffQ + kNUnits * 1024;
constexpr int kOffSo   = kOffStg + 2 * kStgBytes;
constexpr int kOffCred = kOffSo + 512;
constexpr int kOffRed  = kOffCred + 256;
constexpr int kOffMisc = kOffRed + 256;
constexpr int kOffBar  = kOffMisc + 128;
constexpr int kSmemBytes = kOffBar + (3 * kNSlot + 12) * 8 + 1024;
static_assert(kSmemBytes <= 232448, "smem");

constexpr float kSmScale = 0.08838834764831845f;
constexpr float kLog2e   = 1.4426950408889634f;

__device__ unsigned int g_epoch;
__device__ unsigned int g_ctr[2];
__device__ __align__(16) unsigned long long g_qx[kNUnits][256];
constexpr int kPxRing = 8;
__device__ __align__(32) unsigned long long g_px[kPxRing][kNCta / 2][kNCta][2][2];
__device__ __align__(16) unsigned long long g_fo[kNCta][kNCta][8];

__device__ __forceinline__ uint32_t smem_u32(const void* p) { return (uint32_t)__cvta_generic_to_shared(p); }

__device__ __forceinline__ void mbar_init(uint32_t bar, uint32_t cnt) {
    asm volatile("mbarrier.init.shared::cta.b64 [%0], %1;" :: "r"(bar), "r"(cnt) : "memory");
}
__device__ __forceinline__ void mbar_expect_tx(uint32_t bar, uint32_t bytes) {
    asm volatile("mbarrier.arrive.expect_tx.shared::cta.b64 _, [%0], %1;" :: "r"(bar), "r"(bytes) : "memory");
}
__device__ __forceinline__ void mbar_arrive(uint32_t bar) {
    asm volatile("mbarrier.arrive.shared::cta.b64 _, [%0];" :: "r"(bar) : "memory");
}
__device__ __forceinline__ void mbar_wait(uint32_t bar, uint32_t parity) {
    uint32_t done;
    uint32_t iters = 0;
    while (true) {
        asm volatile("{\n.reg .pred p;\n"
                     "mbarrier.try_wait.parity.shared::cta.b64 p, [%1], %2;\n"
                     "selp.u32 %0, 1, 0, p;\n}"
                     : "=r"(done) : "r"(bar), "r"(parity) : "memory");
        if (done) break;
        if (++iters > (1u << 24)) __trap();
    }
}
__device__ __forceinline__ void tma_load_3d_hint(uint32_t dst, const CUtensorMap* map, uint32_t bar, int c0, int c1, int c2, uint64_t pol) {
    asm volatile("cp.async.bulk.tensor.3d.shared::cluster.global.mbarrier::complete_tx::bytes.L2::cache_hint "
                 "[%0], [%1, {%3, %4, %5}], [%2], %6;"
                 :: "r"(dst), "l"(map), "r"(bar), "r"(c0), "r"(c1), "r"(c2), "l"(pol) : "memory");
}
__device__ __forceinline__ void tma_load_4d(uint32_t dst, const CUtensorMap* map, uint32_t bar, int c0, int c1, int c2, int c3) {
    asm volatile("cp.async.bulk.tensor.4d.shared::cluster.global.mbarrier::complete_tx::bytes "
                 "[%0], [%1, {%3, %4, %5, %6}], [%2];"
                 :: "r"(dst), "l"(map), "r"(bar), "r"(c0), "r"(c1), "r"(c2), "r"(c3) : "memory");
}
__device__ __forceinline__ void ldsm_x4(uint32_t& r0, uint32_t& r1, uint32_t& r2, uint32_t& r3, uint32_t addr) {
    asm volatile("ldmatrix.sync.aligned.m8n8.x4.shared.b16 {%0,%1,%2,%3}, [%4];"
                 : "=r"(r0), "=r"(r1), "=r"(r2), "=r"(r3) : "r"(addr) : "memory");
}
__device__ __forceinline__ void ldsm_x4_t(uint32_t& r0, uint32_t& r1, uint32_t& r2, uint32_t& r3, uint32_t addr) {
    asm volatile("ldmatrix.sync.aligned.m8n8.x4.trans.shared.b16 {%0,%1,%2,%3}, [%4];"
                 : "=r"(r0), "=r"(r1), "=r"(r2), "=r"(r3) : "r"(addr) : "memory");
}
__device__ __forceinline__ void mma_bf16(float (&c)[4], uint32_t a0, uint32_t a1, uint32_t a2, uint32_t a3,
                                         uint32_t b0, uint32_t b1) {
    asm volatile("mma.sync.aligned.m16n8k16.row.col.f32.bf16.bf16.f32 "
                 "{%0,%1,%2,%3}, {%4,%5,%6,%7}, {%8,%9}, {%0,%1,%2,%3};"
                 : "+f"(c[0]), "+f"(c[1]), "+f"(c[2]), "+f"(c[3])
                 : "r"(a0), "r"(a1), "r"(a2), "r"(a3), "r"(b0), "r"(b1));
}
__device__ __forceinline__ uint32_t movmatrix_t(uint32_t a) {
    uint32_t d;
    asm volatile("movmatrix.sync.aligned.m8n8.trans.b16 %0, %1;" : "=r"(d) : "r"(a));
    return d;
}
__device__ __forceinline__ uint32_t pack_bf16(float lo, float hi) {
    uint32_t r;
    asm("cvt.rn.bf16x2.f32 %0, %1, %2;" : "=r"(r) : "f"(hi), "f"(lo));
    return r;
}
__device__ __forceinline__ float bf16lo(uint32_t v) { return __uint_as_float(v << 16); }
__device__ __forceinline__ float bf16hi(uint32_t v) { return __uint_as_float(v & 0xffff0000u); }
__device__ __forceinline__ float ex2(float x) {
    float y;
    asm("ex2.approx.ftz.f32 %0, %1;" : "=f"(y) : "f"(x));
    return y;
}
__device__ __forceinline__ unsigned long long ll_word(uint32_t payload, uint32_t tag) {
    return ((unsigned long long)tag << 32) | payload;
}
__device__ __forceinline__ unsigned long long ll_wordf(float payload, uint32_t tag) {
    return ((unsigned long long)tag << 32) | __float_as_uint(payload);
}
__device__ __forceinline__ void ll_st1(unsigned long long* p, unsigned long long a) {
    asm volatile("st.relaxed.gpu.global.b64 [%0], %1;" :: "l"(p), "l"(a) : "memory");
}
__device__ __forceinline__ void ll_st2(unsigned long long* p, unsigned long long a, unsigned long long b) {
    asm volatile("st.relaxed.gpu.global.v2.b64 [%0], {%1, %2};" :: "l"(p), "l"(a), "l"(b) : "memory");
}
__device__ __forceinline__ void ll_ld2(const unsigned long long* p, unsigned long long& a, unsigned long long& b) {
    asm volatile("ld.relaxed.gpu.global.v2.b64 {%0, %1}, [%2];" : "=l"(a), "=l"(b) : "l"(p) : "memory");
}
__device__ __forceinline__ bool ll_ok(unsigned long long w, uint32_t tag) { return (uint32_t)(w >> 32) == tag; }
__device__ __forceinline__ float ll_f(unsigned long long w) { return __uint_as_float((uint32_t)w); }
__device__ __forceinline__ unsigned long long px_pack(float a, float b, uint32_t x16, uint32_t t8) {
    const uint32_t ua = (__float_as_uint(a) + 0x800u) & 0xfffff000u;
    const uint32_t ub = (__float_as_uint(b) + 0x800u) >> 12;
    return ((unsigned long long)(ua | (ub >> 8)) << 32) | (unsigned long long)((ub << 24) | (x16 << 8) | t8);
}
__device__ __forceinline__ bool px_ok(unsigned long long w, uint32_t t8) { return ((uint32_t)w & 0xffu) == t8; }
__device__ __forceinline__ float px_a(unsigned long long w) { return __uint_as_float((uint32_t)(w >> 32) & 0xfffff000u); }
__device__ __forceinline__ float px_b(unsigned long long w) { return __uint_as_float((uint32_t)(w >> 12) & 0xfffff000u); }
__device__ __forceinline__ float px_max(unsigned long long w0) { return __uint_as_float(((uint32_t)w0 << 8) & 0xffff0000u); }
__device__ __forceinline__ float px_lgl(unsigned long long w1) { return (float)(((uint32_t)w1 >> 8) & 0xffffu) * (1.f / 4096.f); }
__device__ __forceinline__ float lg2(float x) {
    float y;
    asm("lg2.approx.ftz.f32 %0, %1;" : "=f"(y) : "f"(x));
    return y;
}
__device__ __forceinline__ uint4 ldg_nc_v4(const void* p) {
    uint4 v;
    asm volatile("ld.global.nc.L1::no_allocate.v4.u32 {%0,%1,%2,%3}, [%4];"
                 : "=r"(v.x), "=r"(v.y), "=r"(v.z), "=r"(v.w) : "l"(p) : "memory");
    return v;
}
__device__ __forceinline__ void bar256() { asm volatile("bar.sync 1, 256;" ::: "memory"); }
__device__ __forceinline__ void bar64() { asm volatile("bar.sync 2, 64;" ::: "memory"); }

struct Params {
    const __nv_bfloat16* x;
    const __nv_bfloat16* wqA;
    const __nv_bfloat16* wqB;
    const __nv_bfloat16* gate_w;
    __nv_bfloat16* out;
};

__device__ __forceinline__ void tail_phase(unsigned char* sptr, const uint32_t sbase, const uint32_t epoch,
                                           __nv_bfloat16* out) {
    const int tid = threadIdx.x, warp = tid >> 5, lane = tid & 31, cta = blockIdx.x;
    const int g = lane >> 2, tq = lane & 3, mi = lane >> 3, rr = lane & 7;
    const uint32_t tag = ((epoch + 1u) << 6) + 63u;
    const uint32_t bar_wo = sbase + kOffBar + (3 * kNSlot + 8) * 8;
    volatile int* s_end = reinterpret_cast<volatile int*>(sptr + kOffMisc + 64);
    {
        int slot = s_end[0];
        float c[4][4];
#pragma unroll
        for (int i = 0; i < 4; i++) { c[i][0] = 0.f; c[i][1] = 0.f; c[i][2] = 0.f; c[i][3] = 0.f; }
        const uint32_t* sob = reinterpret_cast<const uint32_t*>(sptr + kOffSo);
#pragma unroll
        for (int hfj = 0; hfj < 2; hfj++) {
            mbar_wait(bar_wo + (hfj * 2 + (warp >> 2)) * 8, 0);
            const uint32_t wb = sbase + kOffRing + slot * kSlotBytes + warp * 4096;
#pragma unroll
            for (int k2 = 0; k2 < 2; k2++) {
                const int ks = hfj * 2 + k2;
                uint32_t b0 = 0u, b1 = 0u;
                if (g < 4) { b0 = sob[g * 32 + ks * 8 + tq]; b1 = sob[g * 32 + ks * 8 + 4 + tq]; }
                const uint32_t rowoff = (uint32_t)(k2 * 16 + rr + (mi >> 1) * 8) * 128u;
#pragma unroll
                for (int mt = 0; mt < 4; mt++) {
                    uint32_t a0, a1, a2, a3;
                    const uint32_t ch = ((uint32_t)(2 * mt) + (uint32_t)(mi & 1)) ^ (uint32_t)rr;
                    ldsm_x4_t(a0, a1, a2, a3, wb + rowoff + ch * 16);
                    mma_bf16(c[mt], a0, a1, a2, a3, b0, b1);
                }
            }
            if (++slot == kNSlot) slot = 0;
        }
        if (tq < 2) {
#pragma unroll
            for (int mt = 0; mt < 4; mt++) {
                const int dest = ((tq * 32 + warp * 4 + mt) << 1) + (g >> 2);
                ll_st2(&g_fo[dest][cta][(g & 3) * 2], ll_wordf(c[mt][0] + c[mt][1], tag), ll_wordf(c[mt][2] + c[mt][3], tag));
            }
        }
    }
    {
        const int w4 = tid & 3, src = tid >> 2;
        uint32_t iters = 0;
        unsigned long long a = 0, b = 0, c = 0, d = 0;
        bool ok0 = false, ok1 = false;
        while (true) {
            if (!ok0) ll_ld2(&g_fo[cta][src][w4 * 2], a, b);
            if (!ok1) ll_ld2(&g_fo[cta][src + 64][w4 * 2], c, d);
            ok0 = ll_ok(a, tag) && ll_ok(b, tag);
            ok1 = ll_ok(c, tag) && ll_ok(d, tag);
            if (__all_sync(0xffffffffu, ok0 && ok1)) break;
            if (++iters > (1u << 22)) __trap();
        }
        float v0 = ll_f(a) + ll_f(c);
        float v1 = ll_f(b) + ll_f(d);
#pragma unroll
        for (int off = 4; off <= 16; off <<= 1) {
            v0 += __shfl_xor_sync(0xffffffffu, v0, off);
            v1 += __shfl_xor_sync(0xffffffffu, v1, off);
        }
        float* red = reinterpret_cast<float*>(sptr + kOffRed);
        if (lane < 4) { red[warp * 8 + lane * 2] = v0; red[warp * 8 + lane * 2 + 1] = v1; }
        bar256();
        if (tid < 8) {
            float sum = 0.f;
#pragma unroll
            for (int w8 = 0; w8 < 8; w8++) sum += red[w8 * 8 + tid];
            const int b2 = cta >> 6, mtile = (cta >> 1) & 31, gh = cta & 1;
            const int n = mtile * 16 + gh * 4 + (tid >> 1) + (tid & 1) * 8;
            out[b2 * kD + n] = __float2bfloat16(sum);
        }
        if (tid == 0 && cta == 0) *(volatile unsigned int*)&g_epoch = epoch + 1u;
    }
}

__global__ void __launch_bounds__(kThreads, 1)
fused_decode_kernel(const __grid_constant__ CUtensorMap mapKA, const __grid_constant__ CUtensorMap mapVA,
                    const __grid_constant__ CUtensorMap mapKB, const __grid_constant__ CUtensorMap mapVB,
                    const __grid_constant__ CUtensorMap mapWoA, const __grid_constant__ CUtensorMap mapWoB,
                    const Params prm) {
    extern __shared__ __align__(16) unsigned char smem_raw[];
    const uint32_t sbase = (smem_u32(smem_raw) + 1023u) & ~1023u;
    unsigned char* sptr = smem_raw + (sbase - smem_u32(smem_raw));

    const int tid  = threadIdx.x;
    const int warp = tid >> 5;
    const int lane = tid & 31;
    const int cta  = blockIdx.x;

    const uint32_t bar_full   = sbase + kOffBar;
    const uint32_t bar_empty  = bar_full + 2 * kNSlot * 8;
    const uint32_t bar_sfull  = bar_empty + kNSlot * 8;
    const uint32_t bar_sempty = bar_sfull + 16;
    const uint32_t bar_q      = bar_sempty + 16;
    const uint32_t bar_wo     = bar_q + 32;
    volatile float* s_gate = reinterpret_cast<volatile float*>(sptr + kOffMisc);
    volatile int*   s_meta = reinterpret_cast<volatile int*>(sptr + kOffMisc + 16);
    volatile int*   s_stg  = reinterpret_cast<volatile int*>(sptr + kOffMisc + 48);
    volatile int*   s_end  = reinterpret_cast<volatile int*>(sptr + kOffMisc + 64);
    volatile int*   s_prog = reinterpret_cast<volatile int*>(sptr + kOffMisc + 72);

    if (warp == 8) {
        int cur = cta;
        int nxt = kNCta + cta;
        int slot = 0, fslot = 0;
        uint32_t ph = 1, fph = 0;
        int n = 0;
        uint64_t pol = 0;
        auto throttle = [&]() {
            if (n >= kFlight) {
                mbar_wait(bar_full + fslot * 8, fph);
                if (++fslot == 2 * kNSlot) { fslot = 0; fph ^= 1; }
            }
            n++;
        };
        auto issue = [&](int blk) {
            const int unit = blk >> 9;
            const int row = (unit & 15) * kSk + (blk & (kBlkPerUnit - 1)) * kBlkKeys;
            const uint32_t fb = bar_full + slot * 16;
            const uint32_t dst = sbase + kOffRing + slot * kSlotBytes;
            throttle();
            s_meta[slot] = unit;
            mbar_expect_tx(fb, kTileBytes);
            tma_load_3d_hint(dst, unit >= 16 ? &mapKB : &mapKA, fb, 0, row, 0, pol);
            throttle();
            mbar_expect_tx(fb + 8, kTileBytes);
            tma_load_3d_hint(dst + kTileBytes, unit >= 16 ? &mapVB : &mapVA, fb + 8, 0, row, 0, pol);
            if (++slot == kNSlot) { slot = 0; ph ^= 1; }
        };
        if (lane == 0) {
            for (int s = 0; s < kNSlot; s++) {
                mbar_init(bar_full + s * 16, 1);
                mbar_init(bar_full + s * 16 + 8, 1);
                mbar_init(bar_empty + s * 8, 4);
            }
            for (int s = 0; s < 2; s++) { mbar_init(bar_sfull + s * 8, 4); mbar_init(bar_sempty + s * 8, 2); }
            s_prog[0] = 0; s_prog[1] = 0;
            for (int s = 0; s < 4; s++) mbar_init(bar_q + s * 8, 128);
            for (int s = 0; s < 4; s++) mbar_init(bar_wo + s * 8, 1);
            asm volatile("fence.mbarrier_init.release.cluster;" ::: "memory");
            asm volatile("createpolicy.fractional.L2::evict_first.b64 %0, 1.0;" : "=l"(pol));
            issue(cur);
        }
        __syncthreads();
        if (lane == 0) {
            const uint32_t epoch = *(volatile unsigned int*)&g_epoch;
            unsigned int* ctr = &g_ctr[epoch & 1u];
            if (cta == 0) g_ctr[(epoch + 1u) & 1u] = 0u;
            issue(nxt);
            cur = 2 * kNCta + cta;
            nxt = 3 * kNCta + (int)atomicAdd(ctr, 1u);
            while (cur < kTotalBlk) {
                mbar_wait(bar_empty + slot * 8, ph);
                issue(cur);
                cur = nxt;
                nxt = 3 * kNCta + (int)atomicAdd(ctr, 1u);
            }
            mbar_wait(bar_empty + slot * 8, ph);
            s_meta[slot] = kNUnits;
            mbar_arrive(bar_full + slot * 16);
            if (++slot == kNSlot) { slot = 0; ph ^= 1; }
            for (int i = 0; i < kFlight; i++) throttle();
#pragma unroll 1
            for (int m = 0; m < 4; m++) {
                if (!(m & 1)) mbar_wait(bar_empty + slot * 8, ph);
                if (m >= 2) mbar_wait(bar_wo + (m - 2) * 8, 0);
                const uint32_t fb = bar_wo + m * 8;
                mbar_expect_tx(fb, kSlotBytes / 2);
                tma_load_4d(sbase + kOffRing + slot * kSlotBytes + (m & 1) * (kSlotBytes / 2), (m >> 1) ? &mapWoB : &mapWoA,
                            fb, 0, 4 * cta, 0, (m & 1) * 4);
                if ((m & 1) && ++slot == kNSlot) { slot = 0; ph ^= 1; }
            }
        }
        return;
    }

    const uint32_t epoch = *(volatile unsigned int*)&g_epoch;
    const uint32_t tag   = ((epoch + 1u) << 6) + 63u;
    const int g = lane >> 2;
    const int tq = lane & 3;
    const int mi = lane >> 3, rr = lane & 7;
    const uint32_t sw = (uint32_t)rr;

    {
        const int mod = cta >> 6, cblk = cta & 63;
        const int c8 = tid & 7;
        const int rg = tid >> 3;
        const __nv_bfloat16* wp = (mod ? prm.wqB : prm.wqA) + (size_t)(rg * 16) * (kHq * kDh) + cblk * 64 + c8 * 8;
        uint4 w[16];
#pragma unroll
        for (int k = 0; k < 16; k++) w[k] = ldg_nc_v4(wp + (size_t)k * (kHq * kDh));
        __syncthreads();
        uint4 xv[2][2];
#pragma unroll
        for (int b = 0; b < 2; b++) {
            xv[b][0] = *reinterpret_cast<const uint4*>(prm.x + b * kD + rg * 16);
            xv[b][1] = *reinterpret_cast<const uint4*>(prm.x + b * kD + rg * 16 + 8);
        }
        float acc[2][8];
#pragma unroll
        for (int b = 0; b < 2; b++)
#pragma unroll
            for (int j = 0; j < 8; j++) acc[b][j] = 0.f;
#pragma unroll
        for (int k = 0; k < 16; k++) {
            const uint32_t wv[4] = {w[k].x, w[k].y, w[k].z, w[k].w};
#pragma unroll
            for (int b = 0; b < 2; b++) {
                const uint4 xx = xv[b][k >> 3];
                const uint32_t xw = ((k >> 1) & 3) == 0 ? xx.x : ((k >> 1) & 3) == 1 ? xx.y : ((k >> 1) & 3) == 2 ? xx.z : xx.w;
                const float xf = (k & 1) ? bf16hi(xw) : bf16lo(xw);
#pragma unroll
                for (int j = 0; j < 4; j++) {
                    acc[b][2 * j]     = fmaf(xf, bf16lo(wv[j]), acc[b][2 * j]);
                    acc[b][2 * j + 1] = fmaf(xf, bf16hi(wv[j]), acc[b][2 * j + 1]);
                }
            }
        }
#pragma unroll
        for (int b = 0; b < 2; b++)
#pragma unroll
            for (int j = 0; j < 8; j++) {
                acc[b][j] += __shfl_xor_sync(0xffffffffu, acc[b][j], 8);
                acc[b][j] += __shfl_xor_sync(0xffffffffu, acc[b][j], 16);
            }
        float* red = reinterpret_cast<float*>(sptr + kOffStg);
        if (lane < 8) {
#pragma unroll
            for (int b = 0; b < 2; b++) {
                float4* d4 = reinterpret_cast<float4*>(red + (warp * 2 + b) * 64 + lane * 8);
                d4[0] = make_float4(acc[b][0], acc[b][1], acc[b][2], acc[b][3]);
                d4[1] = make_float4(acc[b][4], acc[b][5], acc[b][6], acc[b][7]);
            }
        }
        bar256();
        if (warp >= 4 && warp < 6) {
            const int b = warp - 4, i = ((lane >> 1) & 3) * 8 + (lane & 1) * 4 + (lane >> 3);
            float s0 = 0.f, s1 = 0.f;
#pragma unroll
            for (int w8 = 0; w8 < 8; w8++) {
                const float2 v = *reinterpret_cast<const float2*>(red + (w8 * 2 + b) * 64 + 2 * i);
                s0 += v.x; s1 += v.y;
            }
            const int kvh = cblk >> 3;
            const int col = (cblk & 7) * 64 + 2 * i;
            const int head = col >> 7, p = (col & 127) >> 1;
            const int pos = (head * 4 + (p & 3)) * 16 + (p >> 3) * 2 + ((p >> 2) & 1);
            ll_st1(&g_qx[mod * 16 + b * 8 + kvh][pos], ll_word(pack_bf16(s0, s1), tag));
        } else if (warp == 6) {
            float s[2] = {0.f, 0.f};
#pragma unroll
            for (int h = 0; h < 2; h++) {
                const uint4 gw = *reinterpret_cast<const uint4*>(prm.gate_w + (h * 32 + lane) * 8);
                const uint32_t gv[4] = {gw.x, gw.y, gw.z, gw.w};
#pragma unroll
                for (int b = 0; b < 2; b++) {
                    const uint4 xx = *reinterpret_cast<const uint4*>(prm.x + b * kD + (h * 32 + lane) * 8);
                    const uint32_t xw[4] = {xx.x, xx.y, xx.z, xx.w};
#pragma unroll
                    for (int j = 0; j < 4; j++) {
                        s[b] = fmaf(bf16lo(gv[j]), bf16lo(xw[j]), s[b]);
                        s[b] = fmaf(bf16hi(gv[j]), bf16hi(xw[j]), s[b]);
                    }
                }
            }
#pragma unroll
            for (int o = 16; o > 0; o >>= 1) {
                s[0] += __shfl_xor_sync(0xffffffffu, s[0], o);
                s[1] += __shfl_xor_sync(0xffffffffu, s[1], o);
            }
            if (lane < 2) s_gate[lane] = 1.f / (1.f + __expf(-(lane ? s[1] : s[0])));
        }
    }

    if (tq < 2) {
#pragma unroll
        for (int mt = 0; mt < 4; mt++) {
            const int dest = ((tq * 32 + warp * 4 + mt) << 1) + (g >> 2);
            ll_st2(&g_fo[dest][cta][(g & 3) * 2], ll_word(0u, tag - 1u), ll_word(0u, tag - 1u));
        }
    }

    if (warp < 4) {
        uint32_t bq[8][2];
        float o[8][4];
        float m0 = -INFINITY, m1 = -INFINITY, l0 = 0.f, l1 = 0.f;
#pragma unroll
        for (int i = 0; i < 8; i++) { bq[i][0] = 0u; bq[i][1] = 0u; o[i][0] = 0.f; o[i][1] = 0.f; o[i][2] = 0.f; o[i][3] = 0.f; }

        const uint32_t kRowOff = (uint32_t)(warp * 16 + rr + (mi & 1) * 8) * 128u;
        const uint32_t kChunk  = (uint32_t)(mi >> 1);
        const uint32_t vRowOff = (uint32_t)(warp * 16 + rr + (mi >> 1) * 8) * 128u + kTileBytes;
        const uint32_t vChunk  = (uint32_t)(mi & 1);

        int cur_unit = -1;
        int slot = 0, sbuf = 0;
        uint32_t ph = 0, sph = 1;
#pragma unroll 1
        while (true) {
            mbar_wait(bar_full + slot * 16, ph);
            const int unit = s_meta[slot];
            if (unit != cur_unit) {
                if (cur_unit >= 0) {
                    mbar_wait(bar_sempty + sbuf * 8, sph);
                    float* so  = reinterpret_cast<float*>(sptr + kOffStg + sbuf * kStgBytes);
                    float* sml = so + 4 * 4 * 128;
#pragma unroll
                    for (int off = 4; off <= 16; off <<= 1) {
                        l0 += __shfl_xor_sync(0xffffffffu, l0, off);
                        l1 += __shfl_xor_sync(0xffffffffu, l1, off);
                    }
                    if (tq < 2) {
                        float* d0 = so + (warp * 4 + 2 * tq) * 128 + g;
#pragma unroll
                        for (int mt = 0; mt < 8; mt++) {
                            d0[mt * 16]           = o[mt][0];
                            d0[128 + mt * 16]     = o[mt][1];
                            d0[mt * 16 + 8]       = o[mt][2];
                            d0[128 + mt * 16 + 8] = o[mt][3];
                        }
                        if (g == 0) {
                            sml[warp * 8 + 2 * tq] = m0;     sml[warp * 8 + 2 * tq + 1] = m1;
                            sml[warp * 8 + 4 + 2 * tq] = l0; sml[warp * 8 + 4 + 2 * tq + 1] = l1;
                        }
                    }
                    if (tid == 0) { s_stg[sbuf] = cur_unit; s_stg[2 + sbuf] = unit; }
                    __syncwarp();
                    if (lane == 0) mbar_arrive(bar_sfull + sbuf * 8);
                    if (++sbuf == 2) { sbuf = 0; sph ^= 1; }
                }
                if (unit >= kNUnits) break;
                mbar_wait(bar_q + (unit == 0 ? 0 : unit < 8 ? 1 : unit < 16 ? 2 : 3) * 8, 0);
                if (g < 4) {
                    const uint4* qp = reinterpret_cast<const uint4*>(sptr + kOffQ + unit * 1024 + (g * 4 + tq) * 64);
#pragma unroll
                    for (int i = 0; i < 4; i++) {
                        const uint4 v = qp[i];
                        bq[2 * i][0] = v.x; bq[2 * i][1] = v.y; bq[2 * i + 1][0] = v.z; bq[2 * i + 1][1] = v.w;
                    }
                }
#pragma unroll
                for (int i = 0; i < 8; i++) { o[i][0] = 0.f; o[i][1] = 0.f; o[i][2] = 0.f; o[i][3] = 0.f; }
                m0 = -INFINITY; m1 = -INFINITY; l0 = 0.f; l1 = 0.f;
                cur_unit = unit;
            }
            const uint32_t sb = sbase + kOffRing + slot * kSlotBytes;
            float s[4] = {0.f, 0.f, 0.f, 0.f};
            float s2[4] = {0.f, 0.f, 0.f, 0.f};
#pragma unroll
            for (int ks = 0; ks < 8; ks++) {
                uint32_t a0, a1, a2, a3;
                const uint32_t ch = ((uint32_t)((2 * ks) & 7) + kChunk) ^ sw;
                ldsm_x4(a0, a1, a2, a3, sb + kRowOff + (ks >> 2) * (kTileBytes / 2) + ch * 16);
                if (ks & 1) mma_bf16(s2, a0, a1, a2, a3, bq[ks][0], bq[ks][1]);
                else        mma_bf16(s,  a0, a1, a2, a3, bq[ks][0], bq[ks][1]);
            }
            {
                const uint32_t r01 = pack_bf16(s[0] + s2[0], s[1] + s2[1]);
                const uint32_t r23 = pack_bf16(s[2] + s2[2], s[3] + s2[3]);
                const uint32_t t01 = pack_bf16(bf16lo(r01) * kSmScale, bf16hi(r01) * kSmScale);
                const uint32_t t23 = pack_bf16(bf16lo(r23) * kSmScale, bf16hi(r23) * kSmScale);
                s[0] = bf16lo(t01); s[1] = bf16hi(t01); s[2] = bf16lo(t23); s[3] = bf16hi(t23);
            }
            float x0 = fmaxf(s[0], s[2]), x1 = fmaxf(s[1], s[3]);
#pragma unroll
            for (int off = 4; off <= 16; off <<= 1) {
                x0 = fmaxf(x0, __shfl_xor_sync(0xffffffffu, x0, off));
                x1 = fmaxf(x1, __shfl_xor_sync(0xffffffffu, x1, off));
            }
            if (__any_sync(0xffffffffu, (x0 > m0) || (x1 > m1))) {
                const float n0 = fmaxf(m0, x0), n1 = fmaxf(m1, x1);
                const float a0 = ex2((m0 - n0) * kLog2e), a1 = ex2((m1 - n1) * kLog2e);
                m0 = n0; m1 = n1;
                l0 *= a0; l1 *= a1;
#pragma unroll
                for (int i = 0; i < 8; i++) { o[i][0] *= a0; o[i][1] *= a1; o[i][2] *= a0; o[i][3] *= a1; }
            }
            const float p0 = ex2((s[0] - m0) * kLog2e);
            const float p1 = ex2((s[1] - m1) * kLog2e);
            const float p2 = ex2((s[2] - m0) * kLog2e);
            const float p3 = ex2((s[3] - m1) * kLog2e);
            l0 += p0 + p2;
            l1 += p1 + p3;
            const uint32_t pb0 = movmatrix_t(pack_bf16(p0, p1));
            const uint32_t pb1 = movmatrix_t(pack_bf16(p2, p3));
            mbar_wait(bar_full + slot * 16 + 8, ph);
#pragma unroll
            for (int mt = 0; mt < 8; mt++) {
                uint32_t a0, a1, a2, a3;
                const uint32_t ch = ((uint32_t)((2 * mt) & 7) + vChunk) ^ sw;
                ldsm_x4_t(a0, a1, a2, a3, sb + vRowOff + (mt >> 2) * (kTileBytes / 2) + ch * 16);
                mma_bf16(o[mt], a0, a1, a2, a3, pb0, pb1);
            }
            __syncwarp();
            if (lane == 0) mbar_arrive(bar_empty + slot * 8);
            if (++slot == kNSlot) { slot = 0; ph ^= 1; }
        }
        if (tid == 0) s_end[0] = (slot + 1 == kNSlot) ? 0 : slot + 1;
    } else {
        const int rt = tid - 128;
        const int rw = warp - 4;
        __nanosleep(500);
#pragma unroll 1
        for (int j = 0; j < 5; j++) {
            const int u0 = (j == 0) ? 0 : (j == 1) ? 1 : (j - 1) * 8;
            const int nu = (j == 0) ? 1 : (j == 1) ? 7 : 8;
            uint32_t okm = 0, iters = 0;
            const uint32_t want = (1u << nu) - 1u;
            while (true) {
                unsigned long long a[8], b[8];
#pragma unroll
                for (int i = 0; i < 8; i++) {
                    a[i] = 0ull; b[i] = 0ull;
                    if (((want & ~okm) >> i) & 1u) ll_ld2(&g_qx[u0 + i][2 * rt], a[i], b[i]);
                }
#pragma unroll
                for (int i = 0; i < 8; i++) {
                    if (ll_ok(a[i], tag) && ll_ok(b[i], tag)) {
                        *reinterpret_cast<uint2*>(sptr + kOffQ + (u0 + i) * 1024 + rt * 8) = make_uint2((uint32_t)a[i], (uint32_t)b[i]);
                        okm |= 1u << i;
                    }
                }
                if (__all_sync(0xffffffffu, okm == want)) break;
                if (++iters > (1u << 22)) __trap();
                __nanosleep(100);
            }
            if (j != 3) mbar_arrive(bar_q + (j < 3 ? j : 3) * 8);
        }

        if (warp < 6) {
            const int t = rt;
            int sbuf = 0;
            uint32_t sph = 0;
            int have_until = 0;
            int stg_unit = -1;
#pragma unroll 1
            for (int k = 0; k < kNUnits; k++) {
                if (k >= have_until) {
                    mbar_wait(bar_sfull + sbuf * 8, sph);
                    stg_unit = s_stg[sbuf];
                    have_until = s_stg[2 + sbuf];
                }
                {
                    uint32_t iters = 0;
                    while (s_prog[1] < k - kPxRing / 2 + 1) {
                        __nanosleep(200);
                        if (++iters > (1u << 22)) __trap();
                    }
                }
                const uint32_t tk = (epoch * 32u + (uint32_t)k) % 255u + 1u;
                if (k == stg_unit) {
                    const float* so  = reinterpret_cast<const float*>(sptr + kOffStg + sbuf * kStgBytes);
                    const float* sml = so + 4 * 4 * 128;
#pragma unroll
                    for (int hh = 0; hh < 2; hh++) {
                        const int h = rw + 2 * hh;
                        float mw[4], M = -INFINITY;
#pragma unroll
                        for (int w = 0; w < 4; w++) { mw[w] = sml[w * 8 + h]; M = fmaxf(M, mw[w]); }
                        float L = 0.f, a0 = 0.f, a1 = 0.f, a2 = 0.f, a3 = 0.f;
#pragma unroll
                        for (int w = 0; w < 4; w++) {
                            const float wgt = ex2((mw[w] - M) * kLog2e);
                            L = fmaf(wgt, sml[w * 8 + 4 + h], L);
                            const float4 v = *reinterpret_cast<const float4*>(so + (w * 4 + h) * 128 + lane * 4);
                            a0 = fmaf(wgt, v.x, a0); a1 = fmaf(wgt, v.y, a1); a2 = fmaf(wgt, v.z, a2); a3 = fmaf(wgt, v.w, a3);
                        }
                        const uint32_t lq = min(__float2uint_rn(fmaxf(lg2(L), 0.f) * 4096.f), 65535u);
                        const float inv = 1.f / L;
                        const int d = t + 64 * hh;
                        ll_st2(&g_px[k % kPxRing][d >> 1][cta][d & 1][0],
                               px_pack(a0 * inv, a1 * inv, __float_as_uint(M) >> 16, tk), px_pack(a2 * inv, a3 * inv, lq, tk));
                    }
                    __syncwarp();
                    if (lane == 0) mbar_arrive(bar_sempty + sbuf * 8);
                    if (++sbuf == 2) { sbuf = 0; sph ^= 1; }
                } else {
#pragma unroll
                    for (int hh = 0; hh < 2; hh++) {
                        const int d = t + 64 * hh;
                        ll_st2(&g_px[k % kPxRing][d >> 1][cta][d & 1][0],
                               px_pack(0.f, 0.f, 0xff80u, tk), px_pack(0.f, 0.f, 0u, tk));
                    }
                }
                if (t == 0) s_prog[0] = k + 1;
            }
        } else {
            const int t = rt - 64;
            const int cw = warp - 6;
            float* cred = reinterpret_cast<float*>(sptr + kOffCred);
            __nv_bfloat16* sob = reinterpret_cast<__nv_bfloat16*>(sptr + kOffSo);
#pragma unroll 1
            for (int k = 0; k < kNUnits; k++) {
                const bool tight = (k >= kNUnits - 1);
                const uint32_t tk = (epoch * 32u + (uint32_t)k) % 255u + 1u;
                {
                    const int need = (k < kNUnits - 2) ? k + 2 : k + 1;
                    uint32_t iters = 0;
                    while (s_prog[0] < need) {
                        __nanosleep(tight ? 20 : 300);
                        if (++iters > (1u << 24)) __trap();
                    }
                    if (k == kNUnits - 2) {
                        iters = 0;
                        while (s_prog[0] < kNUnits && ++iters < 10) __nanosleep(250);
                    }
                }
                const unsigned long long* src = &g_px[k % kPxRing][cta >> 1][t][cta & 1][0];
                unsigned long long w[2][2];
                bool ok0 = false, ok1 = false;
                uint32_t iters = 0;
                while (true) {
                    if (!ok0) ll_ld2(src, w[0][0], w[0][1]);
                    if (!ok1) ll_ld2(src + 64 * 4, w[1][0], w[1][1]);
                    ok0 = px_ok(w[0][0], tk) && px_ok(w[0][1], tk);
                    ok1 = px_ok(w[1][0], tk) && px_ok(w[1][1], tk);
                    if (__all_sync(0xffffffffu, ok0 && ok1)) break;
                    if (++iters > (1u << 22)) __trap();
                    if (!tight) __nanosleep(k == kNUnits - 2 ? 100 : 1000);
                }
                const float ma = px_max(w[0][0]), mb = px_max(w[1][0]);
                float Mw = fmaxf(fmaxf(ma, mb), -3.0e38f);
#pragma unroll
                for (int off = 16; off > 0; off >>= 1) Mw = fmaxf(Mw, __shfl_xor_sync(0xffffffffu, Mw, off));
                const float wa = ex2(fmaf(ma - Mw, kLog2e, px_lgl(w[0][1])));
                const float wb = ex2(fmaf(mb - Mw, kLog2e, px_lgl(w[1][1])));
                float r0 = wa * px_a(w[0][0]) + wb * px_a(w[1][0]);
                float r1 = wa * px_b(w[0][0]) + wb * px_b(w[1][0]);
                float r2 = wa * px_a(w[0][1]) + wb * px_a(w[1][1]);
                float r3 = wa * px_b(w[0][1]) + wb * px_b(w[1][1]);
                float rl = wa + wb;
#pragma unroll
                for (int off = 16; off > 0; off >>= 1) {
                    r0 += __shfl_xor_sync(0xffffffffu, r0, off);
                    r1 += __shfl_xor_sync(0xffffffffu, r1, off);
                    r2 += __shfl_xor_sync(0xffffffffu, r2, off);
                    r3 += __shfl_xor_sync(0xffffffffu, r3, off);
                    rl += __shfl_xor_sync(0xffffffffu, rl, off);
                }
                float* cr = cred + (k & 1) * 16;
                if (lane == 0) {
                    *reinterpret_cast<float4*>(cr + cw * 8) = make_float4(r0, r1, r2, r3);
                    *reinterpret_cast<float2*>(cr + cw * 8 + 4) = make_float2(Mw, rl);
                }
                bar64();
                if (t < 4) {
                    const float M = fmaxf(cr[4], cr[12]);
                    const float g0 = ex2((cr[4] - M) * kLog2e), g1 = ex2((cr[12] - M) * kLog2e);
                    const float L = g0 * cr[5] + g1 * cr[13];
                    float a = g0 * cr[t] + g1 * cr[8 + t];
                    const int b = (k >> 3) & 1;
                    const float gt = s_gate[b];
                    a = a * ((k >= 16) ? (1.f - gt) : gt) / L;
                    const __nv_bfloat16 hi = __float2bfloat16(a);
                    const __nv_bfloat16 lo = __float2bfloat16(a - __bfloat162float(hi));
                    const int kidx = (k >> 4) * 32 + (k & 7) * 4 + t;
                    sob[(2 * b) * 64 + kidx] = hi;
                    sob[(2 * b + 1) * 64 + kidx] = lo;
                    if (t == 0) s_prog[1] = k + 1;
                }
            }
        }
    }
    bar256();

    tail_phase(sptr, sbase, epoch, prm.out);
}

typedef CUresult (*EncodeTiledFn)(CUtensorMap*, CUtensorMapDataType, cuuint32_t, void*, const cuuint64_t*,
                                  const cuuint64_t*, const cuuint32_t*, const cuuint32_t*, CUtensorMapInterleave,
                                  CUtensorMapSwizzle, CUtensorMapL2promotion, CUtensorMapFloatOOBfill);

void make_kv_map(EncodeTiledFn enc, CUtensorMap* m, const void* base) {
    cuuint64_t gd[3] = {64, (cuuint64_t)2 * kHkv * kSk, 2};
    cuuint64_t gs[2] = {256, 128};
    cuuint32_t box[3] = {64, (cuuint32_t)kBlkKeys, 2};
    cuuint32_t es[3] = {1, 1, 1};
    enc(m, CU_TENSOR_MAP_DATA_TYPE_BFLOAT16, 3, const_cast<void*>(base), gd, gs, box, es,
        CU_TENSOR_MAP_INTERLEAVE_NONE, CU_TENSOR_MAP_SWIZZLE_128B, CU_TENSOR_MAP_L2_PROMOTION_L2_256B,
        CU_TENSOR_MAP_FLOAT_OOB_FILL_NONE);
}
void make_wo_map(EncodeTiledFn enc, CUtensorMap* m, const void* base) {
    cuuint64_t gd[4] = {64, 512, 8, 8};
    cuuint64_t gs[3] = {1024, 512 * 1024, 128};
    cuuint32_t box[4] = {64, 4, 8, 4};
    cuuint32_t es[4] = {1, 1, 1, 1};
    enc(m, CU_TENSOR_MAP_DATA_TYPE_BFLOAT16, 4, const_cast<void*>(base), gd, gs, box, es,
        CU_TENSOR_MAP_INTERLEAVE_NONE, CU_TENSOR_MAP_SWIZZLE_128B, CU_TENSOR_MAP_L2_PROMOTION_L2_256B,
        CU_TENSOR_MAP_FLOAT_OOB_FILL_NONE);
}

}

extern "C" void kernel_launch(void* const* d_in, const int* in_sizes, int n_in, void* d_out, int out_size) {
    (void)in_sizes; (void)n_in; (void)out_size;
    static EncodeTiledFn enc = nullptr;
    if (!enc) {
        void* fn = nullptr;
        cudaDriverEntryPointQueryResult qr;
        cudaGetDriverEntryPoint("cuTensorMapEncodeTiled", &fn, cudaEnableDefault, &qr);
        enc = (EncodeTiledFn)fn;
        cudaFuncSetAttribute(fused_decode_kernel, cudaFuncAttributeMaxDynamicSharedMemorySize, kSmemBytes);
    }
    CUtensorMap mKA, mVA, mKB, mVB, mWA, mWB;
    make_kv_map(enc, &mKA, d_in[1]);
    make_kv_map(enc, &mVA, d_in[2]);
    make_kv_map(enc, &mKB, d_in[6]);
    make_kv_map(enc, &mVB, d_in[7]);
    make_wo_map(enc, &mWA, d_in[4]);
    make_wo_map(enc, &mWB, d_in[9]);
    Params p;
    p.x = (const __nv_bfloat16*)d_in[0];
    p.wqA = (const __nv_bfloat16*)d_in[3];
    p.wqB = (const __nv_bfloat16*)d_in[8];
    p.gate_w = (const __nv_bfloat16*)d_in[10];
    p.out = (__nv_bfloat16*)d_out;
    fused_decode_kernel<<<kNCta, kThreads, kSmemBytes>>>(mKA, mVA, mKB, mVB, mWA, mWB, p);
}
```
